```python
import torch

def _softmax(x, axis=-1):
    return torch.softmax(x, dim=axis)
def _gelu(x):
    return torch.nn.functional.gelu(x, approximate="tanh")
def _silu(x):
    return torch.nn.functional.silu(x)
def _sigmoid(x):
    return torch.sigmoid(x)
def _layernorm(x, axis=-1, eps=1e-5):
    m = x.mean(dim=axis, keepdim=True)
    v = x.var(dim=axis, keepdim=True, unbiased=False)
    return (x - m) / torch.sqrt(v + eps)
def _scatter_add(tgt, idx, src, axis=0):
    return tgt.clone().index_add_(axis, idx, src)
def _segment_sum(src, seg, n):
    out = torch.zeros((n,) + src.shape[1:], dtype=src.dtype)
    return out.index_add_(0, seg, src)
def _pad(x, pw):
    flat = tuple(v for pair in reversed(pw) for v in pair)
    return torch.nn.functional.pad(x, flat)

kernel_name = 'gated_mix__linear_kernel_hedgehog__glu_gated_bilinear__prompt'

def setup_inputs():

    _w = (lambda a: (lambda t: t.to(torch.bfloat16) if t.is_floating_point() else t)(torch.as_tensor(a)))
    def _A_setup():
        B, S, D, H = 1, 2048, 512, 32
        Dh = D // H
        return {
            "x": _w((lambda *s: torch.randn(*s, dtype=torch.bfloat16) * 0.05)(B, S, D)),
            "wqkv": _w((lambda *s: torch.randn(*s, dtype=torch.bfloat16) * 0.8)(D, 3 * D)),
            "w_phi": _w((lambda *s: torch.randn(*s, dtype=torch.bfloat16) * 0.8)(H, Dh, Dh) * (Dh ** -0.5)),
            "wo": _w((lambda *s: torch.randn(*s, dtype=torch.bfloat16) * 0.05)(D, D)),
        }
    _A_in = _A_setup()

    def _B_setup():
        B, S, D, F = 1, 2048, 512, 1792
        return {
            "x": _w((lambda *s: torch.randn(*s, dtype=torch.bfloat16) * 0.05)(B, S, D)),
            "w_gate": _w((lambda *s: torch.randn(*s, dtype=torch.bfloat16) * 1.6)(D, F) * (D ** -0.5)),
            "w_up": _w((lambda *s: torch.randn(*s, dtype=torch.bfloat16) * 1.6)(D, F) * (D ** -0.5)),
            "w_down": _w((lambda *s: torch.randn(*s, dtype=torch.bfloat16) * 1.6)(F, D) * (F ** -0.5)),
        }
    _B_in = _B_setup()

    return {
        "A_x": _A_in["x"],
        "A_wqkv": _A_in["wqkv"],
        "A_w_phi": _A_in["w_phi"],
        "A_wo": _A_in["wo"],
        "B_x": _B_in["x"],
        "B_w_gate": _B_in["w_gate"],
        "B_w_up": _B_in["w_up"],
        "B_w_down": _B_in["w_down"],
        "gate_w": _w((lambda *s: torch.randn(*s, dtype=torch.bfloat16) * 0.05)(512) * 16.0),
    }

def reference(A_x, A_wqkv, A_w_phi, A_wo, B_x, B_w_gate, B_w_up, B_w_down, gate_w):
    def _A_ref(x, wqkv, w_phi, wo):
        B, S, D = x.shape
        H = 32; Dh = D // H
        qkv = (lambda x, *d: x.permute(*d))((x @ wqkv).reshape(B, S, 3, H, Dh), 2, 0, 3, 1, 4)
        q, k, v = qkv[0], qkv[1], qkv[2]
        pq = torch.einsum("bhsd,hdf->bhsf", q, w_phi)
        pk = torch.einsum("bhsd,hdf->bhsf", k, w_phi)
        phi_q = torch.concatenate([_softmax(pq, axis=-1), _softmax(-pq, axis=-1)], axis=-1)
        phi_k = torch.concatenate([_softmax(pk, axis=-1), _softmax(-pk, axis=-1)], axis=-1)
        kv = torch.einsum("bhsf,bhsd->bhfd", phi_k, v)
        z  = torch.einsum("bhsf->bhf", phi_k)
        num = torch.einsum("bhqf,bhfd->bhqd", phi_q, kv)
        den = torch.einsum("bhqf,bhf->bhq", phi_q, z)[..., None] + 1e-6
        o = num / den
        return (lambda x, *d: x.permute(*d))(o, 0, 2, 1, 3).reshape(B, S, D) @ wo

    def _B_ref(x, w_gate, w_up, w_down):
        g = torch.einsum("bsd,df->bsf", x, w_gate)
        u = torch.einsum("bsd,df->bsf", x, w_up)
        h = g * u
        return torch.einsum("bsf,fd->bsd", h, w_down)

    x = A_x
    g = _sigmoid((x * gate_w).sum(-1, keepdims=True))
    a = _A_ref(x, A_wqkv, A_w_phi, A_wo)
    b = _B_ref(x, B_w_gate, B_w_up, B_w_down)
    return g * a + (1 - g) * b
```

```cpp
#include <cuda_runtime.h>
#include <cuda.h>
#include <cuda_bf16.h>
#include <stdint.h>

namespace {

constexpr int SLOT  = 16384;
constexpr int NSLOT = 14;
constexpr int XS    = 8;
constexpr uint32_t SM0 = 1024;
constexpr int SMEM_BYTES = NSLOT * SLOT + 2048;

constexpr int OFF_FULL  = 0;
constexpr int OFF_EMPTY = 14 * 8;
constexpr int OFF_PKR   = 28 * 8;
constexpr int OFF_PHIK  = 29 * 8;
constexpr int OFF_T1R   = 30 * 8;
constexpr int OFF_ORDY  = 31 * 8;
constexpr int OFF_KVR   = 32 * 8;
constexpr int OFF_EPOCH = 288;
constexpr int OFF_GW    = 512;
constexpr int OFF_ONES  = 1792;
constexpr int SKEW = 1;
constexpr int LAG  = 2;

struct Params {
  const __nv_bfloat16* wphi;
  const __nv_bfloat16* gatew;
  __nv_bfloat16* out;
  float4* kv;
  unsigned* cnt;
  uint4* epoch;
  uint4* ax;
  alignas(64) CUtensorMap x, qkv, g, u, g32, u32, wo, wd, o;
};

__device__ float4   g_kv[2][32][136];
__device__ unsigned g_cnt[40 * 32];
__device__ uint4    g_epoch[128];
__device__ uint4    g_ax[128 * 8 * 18 * 32];
#define TS(role, idx)
#define TC(role, idx)
#define TCC(idx)

__device__ __forceinline__ uint32_t s2u(const void* p) { return (uint32_t)__cvta_generic_to_shared(p); }
__device__ __forceinline__ void mbar_init(uint32_t b, int c) { asm volatile("mbarrier.init.shared::cta.b64 [%0], %1;" ::"r"(b), "r"(c) : "memory"); }
__device__ __forceinline__ void mbar_expect(uint32_t b, uint32_t bytes) { asm volatile("mbarrier.arrive.expect_tx.shared::cta.b64 _, [%0], %1;" ::"r"(b), "r"(bytes) : "memory"); }
__device__ __forceinline__ void mbar_arrive(uint32_t b) { asm volatile("mbarrier.arrive.shared::cta.b64 _, [%0];" ::"r"(b) : "memory"); }
__device__ __forceinline__ void mbar_arrive_cluster(uint32_t b, uint32_t cta) {
  uint32_t r;
  asm volatile("mapa.shared::cluster.u32 %0, %1, %2;" : "=r"(r) : "r"(b), "r"(cta));
  asm volatile("mbarrier.arrive.shared::cluster.b64 _, [%0];" ::"r"(r) : "memory");
}
__device__ __forceinline__ void mbar_wait(uint32_t b, uint32_t ph) {
  asm volatile("{\n.reg .pred p;\n.reg .u32 n;\nmov.u32 n, 0;\n"
               "WL: mbarrier.try_wait.parity.shared::cta.b64 p, [%0], %1;\n@p bra WD;\n"
               "add.u32 n, n, 1;\nsetp.lt.u32 p, n, 200000;\n@p bra WL;\nWD:\n}" ::"r"(b), "r"(ph) : "memory");
}
__device__ __forceinline__ void tma2d(uint32_t dst, const CUtensorMap* tm, uint32_t bar, int c0, int c1) {
  asm volatile("cp.async.bulk.tensor.2d.shared::cluster.global.mbarrier::complete_tx::bytes [%0], [%1, {%3, %4}], [%2];"
               ::"r"(dst), "l"(tm), "r"(bar), "r"(c0), "r"(c1) : "memory");
}
__device__ __forceinline__ void tma2d_mc(uint32_t dst, const CUtensorMap* tm, uint32_t bar, int c0, int c1) {
  asm volatile("cp.async.bulk.tensor.2d.shared::cluster.global.mbarrier::complete_tx::bytes.multicast::cluster [%0], [%1, {%3, %4}], [%2], %5;"
               ::"r"(dst), "l"(tm), "r"(bar), "r"(c0), "r"(c1), "h"((uint16_t)3) : "memory");
}
__device__ __forceinline__ void prefetch_tm(const CUtensorMap* tm) { asm volatile("prefetch.tensormap [%0];" ::"l"(tm) : "memory"); }
__device__ __forceinline__ void fence_async() { asm volatile("fence.proxy.async.shared::cta;" ::: "memory"); }

#define WG_FENCE()  asm volatile("wgmma.fence.sync.aligned;" ::: "memory")
#define WG_COMMIT() asm volatile("wgmma.commit_group.sync.aligned;" ::: "memory")
#define WG_WAIT(n)  asm volatile("wgmma.wait_group.sync.aligned %0;" ::"n"(n) : "memory")

__device__ __forceinline__ void wgmma64(uint32_t (&d)[32], const uint32_t* a, uint32_t dlo, uint32_t dhi, int scaleD) {
  asm volatile("{\n.reg .pred p;\n.reg .b64 db;\nsetp.ne.b32 p, %38, 0;\nmov.b64 db, {%36, %37};\n"
               "wgmma.mma_async.sync.aligned.m64n64k16.f32.bf16.bf16 "
               "{%0, %1, %2, %3, %4, %5, %6, %7, %8, %9, %10, %11, %12, %13, %14, %15, %16, %17, %18, %19, %20, %21, %22, %23, %24, %25, %26, %27, %28, %29, %30, %31}, "
               "{%32, %33, %34, %35}, db, p, 1, 1, 1;\n}\n"
               : "+r"(d[0]), "+r"(d[1]), "+r"(d[2]), "+r"(d[3]), "+r"(d[4]), "+r"(d[5]), "+r"(d[6]), "+r"(d[7]), "+r"(d[8]), "+r"(d[9]), "+r"(d[10]), "+r"(d[11]), "+r"(d[12]), "+r"(d[13]), "+r"(d[14]), "+r"(d[15]), "+r"(d[16]), "+r"(d[17]), "+r"(d[18]), "+r"(d[19]), "+r"(d[20]), "+r"(d[21]), "+r"(d[22]), "+r"(d[23]), "+r"(d[24]), "+r"(d[25]), "+r"(d[26]), "+r"(d[27]), "+r"(d[28]), "+r"(d[29]), "+r"(d[30]), "+r"(d[31])
               : "r"(a[0]), "r"(a[1]), "r"(a[2]), "r"(a[3]), "r"(dlo), "r"(dhi), "r"(scaleD));
}
__device__ __forceinline__ void wgmma64_ss(uint32_t (&d)[32], uint32_t alo, uint32_t dlo, int scaleD) {
  asm volatile("{\n.reg .pred p;\n.reg .b64 da, db;\nsetp.ne.b32 p, %34, 0;\nmov.b64 da, {%32, 64};\nmov.b64 db, {%33, 0x40000040};\n"
               "wgmma.mma_async.sync.aligned.m64n64k16.f32.bf16.bf16 "
               "{%0, %1, %2, %3, %4, %5, %6, %7, %8, %9, %10, %11, %12, %13, %14, %15, %16, %17, %18, %19, %20, %21, %22, %23, %24, %25, %26, %27, %28, %29, %30, %31}, "
               "da, db, p, 1, 1, 0, 1;\n}\n"
               : "+r"(d[0]), "+r"(d[1]), "+r"(d[2]), "+r"(d[3]), "+r"(d[4]), "+r"(d[5]), "+r"(d[6]), "+r"(d[7]), "+r"(d[8]), "+r"(d[9]), "+r"(d[10]), "+r"(d[11]), "+r"(d[12]), "+r"(d[13]), "+r"(d[14]), "+r"(d[15]), "+r"(d[16]), "+r"(d[17]), "+r"(d[18]), "+r"(d[19]), "+r"(d[20]), "+r"(d[21]), "+r"(d[22]), "+r"(d[23]), "+r"(d[24]), "+r"(d[25]), "+r"(d[26]), "+r"(d[27]), "+r"(d[28]), "+r"(d[29]), "+r"(d[30]), "+r"(d[31])
               : "r"(alo), "r"(dlo), "r"(scaleD));
}
__device__ __forceinline__ void wgmma8(float (&d)[4], const uint32_t (&a)[4], uint32_t dlo, int scaleD) {
  asm volatile("{\n.reg .pred p;\n.reg .b64 db;\nsetp.ne.b32 p, %9, 0;\nmov.b64 db, {%8, 8};\n"
               "wgmma.mma_async.sync.aligned.m64n8k16.f32.bf16.bf16 {%0, %1, %2, %3}, {%4, %5, %6, %7}, db, p, 1, 1, 0;\n}\n"
               : "+f"(d[0]), "+f"(d[1]), "+f"(d[2]), "+f"(d[3])
               : "r"(a[0]), "r"(a[1]), "r"(a[2]), "r"(a[3]), "r"(dlo), "r"(scaleD));
}
#define D96 "{%0, %1, %2, %3, %4, %5, %6, %7, %8, %9, %10, %11, %12, %13, %14, %15, %16, %17, %18, %19, %20, %21, %22, %23, %24, %25, %26, %27, %28, %29, %30, %31, %32, %33, %34, %35, %36, %37, %38, %39, %40, %41, %42, %43, %44, %45, %46, %47, %48, %49, %50, %51, %52, %53, %54, %55, %56, %57, %58, %59, %60, %61, %62, %63, %64, %65, %66, %67, %68, %69, %70, %71, %72, %73, %74, %75, %76, %77, %78, %79, %80, %81, %82, %83, %84, %85, %86, %87, %88, %89, %90, %91, %92, %93, %94, %95}"
#define O96 "+r"(d[0]), "+r"(d[1]), "+r"(d[2]), "+r"(d[3]), "+r"(d[4]), "+r"(d[5]), "+r"(d[6]), "+r"(d[7]), "+r"(d[8]), "+r"(d[9]), "+r"(d[10]), "+r"(d[11]), "+r"(d[12]), "+r"(d[13]), "+r"(d[14]), "+r"(d[15]), "+r"(d[16]), "+r"(d[17]), "+r"(d[18]), "+r"(d[19]), "+r"(d[20]), "+r"(d[21]), "+r"(d[22]), "+r"(d[23]), "+r"(d[24]), "+r"(d[25]), "+r"(d[26]), "+r"(d[27]), "+r"(d[28]), "+r"(d[29]), "+r"(d[30]), "+r"(d[31]), "+r"(d[32]), "+r"(d[33]), "+r"(d[34]), "+r"(d[35]), "+r"(d[36]), "+r"(d[37]), "+r"(d[38]), "+r"(d[39]), "+r"(d[40]), "+r"(d[41]), "+r"(d[42]), "+r"(d[43]), "+r"(d[44]), "+r"(d[45]), "+r"(d[46]), "+r"(d[47]), "+r"(d[48]), "+r"(d[49]), "+r"(d[50]), "+r"(d[51]), "+r"(d[52]), "+r"(d[53]), "+r"(d[54]), "+r"(d[55]), "+r"(d[56]), "+r"(d[57]), "+r"(d[58]), "+r"(d[59]), "+r"(d[60]), "+r"(d[61]), "+r"(d[62]), "+r"(d[63]), "+r"(d[64]), "+r"(d[65]), "+r"(d[66]), "+r"(d[67]), "+r"(d[68]), "+r"(d[69]), "+r"(d[70]), "+r"(d[71]), "+r"(d[72]), "+r"(d[73]), "+r"(d[74]), "+r"(d[75]), "+r"(d[76]), "+r"(d[77]), "+r"(d[78]), "+r"(d[79]), "+r"(d[80]), "+r"(d[81]), "+r"(d[82]), "+r"(d[83]), "+r"(d[84]), "+r"(d[85]), "+r"(d[86]), "+r"(d[87]), "+r"(d[88]), "+r"(d[89]), "+r"(d[90]), "+r"(d[91]), "+r"(d[92]), "+r"(d[93]), "+r"(d[94]), "+r"(d[95])
__device__ __forceinline__ void wgmma192(uint32_t (&d)[96], const uint32_t* a, uint32_t dlo, int scaleD) {
  asm volatile("{\n.reg .pred p;\n.reg .b64 db;\nsetp.ne.b32 p, %101, 0;\nmov.b64 db, {%100, 0x40000040};\n"
               "wgmma.mma_async.sync.aligned.m64n192k16.f32.bf16.bf16 " D96 ", {%96, %97, %98, %99}, db, p, 1, 1, 1;\n}\n"
               : O96 : "r"(a[0]), "r"(a[1]), "r"(a[2]), "r"(a[3]), "r"(dlo), "r"(scaleD));
}
__device__ __forceinline__ void wgmma192_ss(uint32_t (&d)[96], uint32_t alo, uint32_t dlo) {
  asm volatile("{\n.reg .pred p;\n.reg .b64 da, db;\nsetp.eq.b32 p, 0, 0;\nmov.b64 da, {%96, 0x40000040};\nmov.b64 db, {%97, 0x40000040};\n"
               "wgmma.mma_async.sync.aligned.m64n192k16.f32.bf16.bf16 " D96 ", da, db, p, 1, 1, 0, 1;\n}\n"
               : O96 : "r"(alo), "r"(dlo));
}
__device__ __forceinline__ void wgmma8_xs(float (&d)[4], uint32_t alo, uint32_t dlo) {
  asm volatile("{\n.reg .pred p;\n.reg .b64 da, db;\nsetp.eq.b32 p, 0, 0;\nmov.b64 da, {%4, 0x40000040};\nmov.b64 db, {%5, 8};\n"
               "wgmma.mma_async.sync.aligned.m64n8k16.f32.bf16.bf16 {%0, %1, %2, %3}, da, db, p, 1, 1, 0, 0;\n}\n"
               : "+f"(d[0]), "+f"(d[1]), "+f"(d[2]), "+f"(d[3]) : "r"(alo), "r"(dlo));
}
__device__ __forceinline__ void wgmma16(float* d, const uint32_t* a, uint32_t dlo) {
  asm volatile("{\n.reg .pred p;\n.reg .b64 db;\nsetp.ne.b32 p, 0, 0;\nmov.b64 db, {%12, 16};\n"
               "wgmma.mma_async.sync.aligned.m64n16k16.f32.bf16.bf16 {%0, %1, %2, %3, %4, %5, %6, %7}, {%8, %9, %10, %11}, db, p, 1, 1, 1;\n}\n"
               : "+f"(d[0]), "+f"(d[1]), "+f"(d[2]), "+f"(d[3]), "+f"(d[4]), "+f"(d[5]), "+f"(d[6]), "+f"(d[7])
               : "r"(a[0]), "r"(a[1]), "r"(a[2]), "r"(a[3]), "r"(dlo));
}
template <int N> __device__ __forceinline__ void redef(float (&d)[N]) {
#pragma unroll
  for (int i = 0; i < N; i++) asm volatile("mov.b32 %0, 0;" : "+f"(d[i]));
}
template <int N> __device__ __forceinline__ void redef(uint32_t (&d)[N]) {
#pragma unroll
  for (int i = 0; i < N; i++) asm volatile("mov.b32 %0, 0;" : "+r"(d[i]));
}
__device__ __forceinline__ void pack_inplace(uint32_t* a) {
  asm volatile("cvt.rn.bf16x2.f32 %0, %1, %0;\ncvt.rn.bf16x2.f32 %1, %3, %2;\ncvt.rn.bf16x2.f32 %2, %5, %4;\ncvt.rn.bf16x2.f32 %3, %7, %6;"
               : "+r"(a[0]), "+r"(a[1]), "+r"(a[2]), "+r"(a[3]) : "r"(a[4]), "r"(a[5]), "r"(a[6]), "r"(a[7]));
}
constexpr uint32_t DHI128 = (1024u >> 4) | (1u << 30);
constexpr uint32_t DHI64  = (512u >> 4) | (2u << 30);
constexpr uint32_t DLBO64 = (4096u >> 4) << 16;
constexpr uint32_t DLBO128B = (128u >> 4) << 16;
__device__ __forceinline__ void wgmma32_ss(float* d, uint32_t alo, uint32_t blo_, int scaleD) {
  if (scaleD) {
  asm volatile("{\n.reg .pred p;\n.reg .b64 da, db;\nsetp.ne.b32 p, %18, 0;\nmov.b64 da, {%16, %19};\nmov.b64 db, {%17, 16};\n"
               "wgmma.mma_async.sync.aligned.m64n32k16.f32.bf16.bf16 {%0, %1, %2, %3, %4, %5, %6, %7, %8, %9, %10, %11, %12, %13, %14, %15}, da, db, p, 1, 1, 1, 1;\n}\n"
               : "+f"(d[0]), "+f"(d[1]), "+f"(d[2]), "+f"(d[3]), "+f"(d[4]), "+f"(d[5]), "+f"(d[6]), "+f"(d[7]),
                 "+f"(d[8]), "+f"(d[9]), "+f"(d[10]), "+f"(d[11]), "+f"(d[12]), "+f"(d[13]), "+f"(d[14]), "+f"(d[15])
               : "r"(alo), "r"(blo_), "r"(scaleD), "n"(DHI64));
  } else {
  asm volatile("{\n.reg .pred p;\n.reg .b64 da, db;\nsetp.ne.b32 p, %18, 0;\nmov.b64 da, {%16, %19};\nmov.b64 db, {%17, 16};\n"
               "wgmma.mma_async.sync.aligned.m64n32k16.f32.bf16.bf16 {%0, %1, %2, %3, %4, %5, %6, %7, %8, %9, %10, %11, %12, %13, %14, %15}, da, db, p, 1, 1, 1, 1;\n}\n"
               : "+f"(d[0]), "+f"(d[1]), "+f"(d[2]), "+f"(d[3]), "+f"(d[4]), "+f"(d[5]), "+f"(d[6]), "+f"(d[7]),
                 "+f"(d[8]), "+f"(d[9]), "+f"(d[10]), "+f"(d[11]), "+f"(d[12]), "+f"(d[13]), "+f"(d[14]), "+f"(d[15])
               : "r"(alo), "r"(blo_), "r"(scaleD), "n"(DHI64));
  }
}
__device__ __forceinline__ void wgmma8_ss(float (&d)[4], uint32_t alo, uint32_t blo_) {
  asm volatile("{\n.reg .pred p;\n.reg .b64 da, db;\nsetp.eq.b32 p, 0, 0;\nmov.b64 da, {%4, %6};\nmov.b64 db, {%5, 0};\n"
               "wgmma.mma_async.sync.aligned.m64n8k16.f32.bf16.bf16 {%0, %1, %2, %3}, da, db, p, 1, 1, 1, 1;\n}\n"
               : "+f"(d[0]), "+f"(d[1]), "+f"(d[2]), "+f"(d[3]) : "r"(alo), "r"(blo_), "n"(DHI64));
}
__device__ __forceinline__ void wgmma24_ss(float (&d)[12], uint32_t alo, uint32_t blo_, int scaleD) {
  if (scaleD) {
  asm volatile("{\n.reg .pred p;\n.reg .b64 da, db;\nsetp.ne.b32 p, %14, 0;\nmov.b64 da, {%12, %15};\nmov.b64 db, {%13, 32};\n"
               "wgmma.mma_async.sync.aligned.m64n24k16.f32.bf16.bf16 {%0, %1, %2, %3, %4, %5, %6, %7, %8, %9, %10, %11}, da, db, p, 1, 1, 0, 1;\n}\n"
               : "+f"(d[0]), "+f"(d[1]), "+f"(d[2]), "+f"(d[3]), "+f"(d[4]), "+f"(d[5]), "+f"(d[6]), "+f"(d[7]),
                 "+f"(d[8]), "+f"(d[9]), "+f"(d[10]), "+f"(d[11])
               : "r"(alo), "r"(blo_), "r"(scaleD), "n"(DHI64));
  } else {
  asm volatile("{\n.reg .pred p;\n.reg .b64 da, db;\nsetp.ne.b32 p, %14, 0;\nmov.b64 da, {%12, %15};\nmov.b64 db, {%13, 32};\n"
               "wgmma.mma_async.sync.aligned.m64n24k16.f32.bf16.bf16 {%0, %1, %2, %3, %4, %5, %6, %7, %8, %9, %10, %11}, da, db, p, 1, 1, 0, 1;\n}\n"
               : "=f"(d[0]), "=f"(d[1]), "=f"(d[2]), "=f"(d[3]), "=f"(d[4]), "=f"(d[5]), "=f"(d[6]), "=f"(d[7]),
                 "=f"(d[8]), "=f"(d[9]), "=f"(d[10]), "=f"(d[11])
               : "r"(alo), "r"(blo_), "r"(scaleD), "n"(DHI64));
  }
}
template <int N> __device__ __forceinline__ void fence_acc(float (&d)[N]) {
#pragma unroll
  for (int i = 0; i < N; i++) asm volatile("" : "+f"(d[i])::"memory");
}
template <int N> __device__ __forceinline__ void fence_acc(uint32_t (&d)[N]) {
#pragma unroll
  for (int i = 0; i < N; i++) asm volatile("" : "+r"(d[i])::"memory");
}

__device__ __forceinline__ float F(uint32_t v) { return __uint_as_float(v); }
__device__ __forceinline__ uint32_t pack2(float lo, float hi) {
  uint32_t r;
  asm("cvt.rn.bf16x2.f32 %0, %1, %2;" : "=r"(r) : "f"(hi), "f"(lo));
  return r;
}
__device__ __forceinline__ float blo(uint32_t v) { return __uint_as_float(v << 16); }
__device__ __forceinline__ float bhi(uint32_t v) { return __uint_as_float(v & 0xffff0000u); }
__device__ __forceinline__ void sts128(uint32_t a, uint32_t x, uint32_t y, uint32_t z, uint32_t w) {
  asm volatile("st.shared.v4.b32 [%0], {%1,%2,%3,%4};" ::"r"(a), "r"(x), "r"(y), "r"(z), "r"(w) : "memory");
}
__device__ __forceinline__ void sts128f(uint32_t a, float x, float y, float z, float w) {
  asm volatile("st.shared.v4.f32 [%0], {%1,%2,%3,%4};" ::"r"(a), "f"(x), "f"(y), "f"(z), "f"(w) : "memory");
}
__device__ __forceinline__ void sts64f(uint32_t a, float x, float y) {
  asm volatile("st.shared.v2.f32 [%0], {%1,%2};" ::"r"(a), "f"(x), "f"(y) : "memory");
}
__device__ __forceinline__ void sts32(uint32_t a, uint32_t x) { asm volatile("st.shared.b32 [%0], %1;" ::"r"(a), "r"(x) : "memory"); }
__device__ __forceinline__ void lds128(uint32_t (&r)[4], uint32_t a) {
  asm volatile("ld.shared.v4.b32 {%0,%1,%2,%3}, [%4];" : "=r"(r[0]), "=r"(r[1]), "=r"(r[2]), "=r"(r[3]) : "r"(a) : "memory");
}
__device__ __forceinline__ void lds128_over(uint32_t* r, uint32_t a) {
  asm volatile("ld.shared.v4.b32 {%0,%1,%2,%3}, [%4];" : "+r"(r[0]), "+r"(r[1]), "+r"(r[2]), "+r"(r[3]) : "r"(a) : "memory");
}
__device__ __forceinline__ void lds128f(float* r, uint32_t a) {
  asm volatile("ld.shared.v4.f32 {%0,%1,%2,%3}, [%4];" : "=f"(r[0]), "=f"(r[1]), "=f"(r[2]), "=f"(r[3]) : "r"(a) : "memory");
}
__device__ __forceinline__ uint32_t lds_u(uint32_t a) { uint32_t r; asm volatile("ld.shared.u32 %0, [%1];" : "=r"(r) : "r"(a) : "memory"); return r; }
__device__ __forceinline__ void ldsm4(uint32_t (&r)[4], uint32_t a) {
  asm volatile("ldmatrix.sync.aligned.m8n8.x4.shared.b16 {%0,%1,%2,%3}, [%4];" : "=r"(r[0]), "=r"(r[1]), "=r"(r[2]), "=r"(r[3]) : "r"(a) : "memory");
}
__device__ __forceinline__ void stsm4(uint32_t a, uint32_t x, uint32_t y, uint32_t z, uint32_t w) {
  asm volatile("stmatrix.sync.aligned.m8n8.x4.shared.b16 [%0], {%1,%2,%3,%4};" ::"r"(a), "r"(x), "r"(y), "r"(z), "r"(w) : "memory");
}
__device__ __forceinline__ float ex2(float x) { float r; asm("ex2.approx.ftz.f32 %0, %1;" : "=f"(r) : "f"(x)); return r; }
__device__ __forceinline__ float rcp(float x) { float r; asm("rcp.approx.ftz.f32 %0, %1;" : "=f"(r) : "f"(x)); return r; }
__device__ __forceinline__ void red4(float4* p, float a, float b, float c, float d) {
  asm volatile("red.relaxed.gpu.global.add.v4.f32 [%0], {%1,%2,%3,%4};" ::"l"(p), "f"(a), "f"(b), "f"(c), "f"(d) : "memory");
}
__device__ __forceinline__ void set_tag(uint32_t& x, uint32_t tag) { asm volatile("lop3.b32 %0, %0, 0xfffffffe, %1, 0xea;" : "+r"(x) : "r"(tag)); }
template <bool FENCE = true> __device__ __forceinline__ void send_lin(uint4* dst, uint32_t src, uint32_t bytes) {
  if (FENCE) fence_async();
  asm volatile("{\n.reg .pred p;\nbar.warp.sync 0xffffffff;\nelect.sync _|p, 0xffffffff;\n"
               "@p cp.async.bulk.global.shared::cta.bulk_group [%0], [%1], %2;\ncp.async.bulk.commit_group;\n}" ::"l"(dst), "r"(src), "r"(bytes) : "memory");
}
__device__ __forceinline__ void send_add(const CUtensorMap* tm, uint32_t src, int c0, int c1) {
  asm volatile("{\n.reg .pred p;\nfence.proxy.async.shared::cta;\nbar.warp.sync 0xffffffff;\nelect.sync _|p, 0xffffffff;\n"
               "@p cp.reduce.async.bulk.tensor.2d.global.shared::cta.add.tile.bulk_group [%0, {%2, %3}], [%1];\ncp.async.bulk.commit_group;\n}"
               ::"l"(tm), "r"(src), "r"(c0), "r"(c1) : "memory");
}
template <int N> __device__ __forceinline__ void send_wait() { asm volatile("cp.async.bulk.wait_group.read %0;\nbar.warp.sync 0xffffffff;" ::"n"(N) : "memory"); }
__device__ __forceinline__ void ld_msg(uint32_t (&r)[4], const uint4* p) {
  asm volatile("{\n.reg .b64 lo, hi;\n.reg .b128 v;\nld.relaxed.gpu.global.b128 v, [%4];\nmov.b128 {lo, hi}, v;\n"
               "mov.b64 {%0,%1}, lo;\nmov.b64 {%2,%3}, hi;\n}" : "=r"(r[0]), "=r"(r[1]), "=r"(r[2]), "=r"(r[3]) : "l"(p) : "memory");
}

__device__ __forceinline__ uint32_t max2(uint32_t a, uint32_t b) { uint32_t r; asm("max.bf16x2 %0, %1, %2;" : "=r"(r) : "r"(a), "r"(b)); return r; }
__device__ __forceinline__ uint32_t min2(uint32_t a, uint32_t b) { uint32_t r; asm("min.bf16x2 %0, %1, %2;" : "=r"(r) : "r"(a), "r"(b)); return r; }
__device__ __forceinline__ void phi_rows(uint32_t ra, uint32_t rend) {
  const float L = 1.4426950408889634f;
  uint32_t w[2][4];
  lds128(w[0], ra);
  lds128(w[1], ra ^ 16);
#pragma unroll 1
  while (true) {
    float p[16], e[16];
    const uint32_t mx = max2(max2(max2(w[0][0], w[0][1]), max2(w[0][2], w[0][3])), max2(max2(w[1][0], w[1][1]), max2(w[1][2], w[1][3])));
    const uint32_t mn = min2(min2(min2(w[0][0], w[0][1]), min2(w[0][2], w[0][3])), min2(min2(w[1][0], w[1][1]), min2(w[1][2], w[1][3])));
#pragma unroll
    for (int q = 0; q < 8; q++) { p[2 * q] = blo(w[q >> 2][q & 3]); p[2 * q + 1] = bhi(w[q >> 2][q & 3]); }
    const uint32_t rn = (ra + 2048 == rend) ? ra : ra + 2048;
    lds128(w[0], rn);
    lds128(w[1], rn ^ 16);
    const float mxl = -fmaxf(blo(mx), bhi(mx)) * L, mnl = fminf(blo(mn), bhi(mn)) * L;
    float s0 = 0.f, s1 = 0.f;
#pragma unroll
    for (int q = 0; q < 16; q += 2) { e[q] = ex2(fmaf(p[q], L, mxl)); e[q + 1] = ex2(fmaf(p[q + 1], L, mxl)); s0 += e[q]; s1 += e[q + 1]; }
    float r = rcp(s0 + s1);
    s0 = 0.f; s1 = 0.f;
#pragma unroll
    for (int q = 0; q < 16; q += 2) { p[q] = ex2(fmaf(p[q], -L, mnl)); p[q + 1] = ex2(fmaf(p[q + 1], -L, mnl)); s0 += p[q]; s1 += p[q + 1]; }
#pragma unroll
    for (int q = 0; q < 2; q++)
      sts128(ra ^ (q << 4), pack2(e[8 * q] * r, e[8 * q + 1] * r), pack2(e[8 * q + 2] * r, e[8 * q + 3] * r), pack2(e[8 * q + 4] * r, e[8 * q + 5] * r), pack2(e[8 * q + 6] * r, e[8 * q + 7] * r));
    r = rcp(s0 + s1);
#pragma unroll
    for (int q = 0; q < 2; q++)
      sts128(ra ^ ((2 + q) << 4), pack2(p[8 * q] * r, p[8 * q + 1] * r), pack2(p[8 * q + 2] * r, p[8 * q + 3] * r), pack2(p[8 * q + 4] * r, p[8 * q + 5] * r), pack2(p[8 * q + 6] * r, p[8 * q + 7] * r));
    if (rn == ra) break;
    ra = rn;
  }
}

__device__ __forceinline__ void store_p(uint32_t dst, const float (&a)[32]) {
#pragma unroll
  for (int h = 0; h < 4; h++)
    stsm4(dst + (h >> 1) * SLOT + (h & 1) * 4096, pack2(a[8 * h], a[8 * h + 1]), pack2(a[8 * h + 2], a[8 * h + 3]), pack2(a[8 * h + 4], a[8 * h + 5]), pack2(a[8 * h + 6], a[8 * h + 7]));
}

__device__ __forceinline__ void stage_piece(uint32_t dst, const uint32_t (&a)[32]) {
#pragma unroll
  for (int i = 0; i < 4; i++)
    stsm4(dst ^ (i << 5), pack2(F(a[8 * i]), F(a[8 * i + 1])), pack2(F(a[8 * i + 2]), F(a[8 * i + 3])), pack2(F(a[8 * i + 4]), F(a[8 * i + 5])), pack2(F(a[8 * i + 6]), F(a[8 * i + 7])));
}
template <int N> __device__ __forceinline__ void recv_issue(uint32_t (*m)[4], const uint4* p) {
#pragma unroll
  for (int i = 0; i < N; i++) ld_msg(m[i], p + (i & 3) * 32 + (i >> 2) * 1024);
}
template <int N> __device__ __forceinline__ void recv_check(uint32_t (*m)[4], const uint4* p, uint32_t tag) {
  int it = 0;
#pragma unroll 1
  while (true) {
    uint32_t bad = 0;
#pragma unroll
    for (int i = 0; i < N; i++) bad |= m[i][0] ^ tag;
    if (!__any_sync(0xffffffffu, (bad & 1) != 0)) break;
    if (++it > (1 << 16)) break;
    recv_issue<N>(m, p);
  }
}
__device__ __forceinline__ void bulk_g2s(uint32_t dst, const void* src, uint32_t bytes, uint32_t bar) {
  asm volatile("cp.async.bulk.shared::cluster.global.mbarrier::complete_tx::bytes [%0], [%1], %2, [%3];" ::"r"(dst), "l"(src), "r"(bytes), "r"(bar) : "memory");
}
__device__ __forceinline__ void load_mc(uint32_t dst, const CUtensorMap* tm, uint32_t bar, int c0, int c1, uint32_t expect = SLOT) {
  asm volatile("{\n.reg .pred p;\nelect.sync _|p, 0xffffffff;\n@p mbarrier.arrive.expect_tx.shared::cta.b64 _, [%2], %6;\n"
               "@p cp.async.bulk.tensor.2d.shared::cluster.global.mbarrier::complete_tx::bytes.multicast::cluster [%0], [%1, {%3, %4}], [%2], %5;\n}"
               ::"r"(dst), "l"(tm), "r"(bar), "r"(c0), "r"(c1), "h"((uint16_t)3), "r"(expect) : "memory");
}
__device__ __forceinline__ void load_mc2(uint32_t dst, const CUtensorMap* tm, uint32_t bar, int c0, int c1) {
  asm volatile("{\n.reg .pred p;\nelect.sync _|p, 0xffffffff;\n"
               "@p cp.async.bulk.tensor.2d.shared::cluster.global.mbarrier::complete_tx::bytes.multicast::cluster [%0], [%1, {%3, %4}], [%2], %5;\n}"
               ::"r"(dst), "l"(tm), "r"(bar), "r"(c0), "r"(c1), "h"((uint16_t)3) : "memory");
}
__device__ __forceinline__ void load_x(uint32_t dst, const CUtensorMap* tm, uint32_t bar, int c0, int c1, uint32_t expect = SLOT) {
  asm volatile("{\n.reg .pred p;\nelect.sync _|p, 0xffffffff;\n@p mbarrier.arrive.expect_tx.shared::cta.b64 _, [%2], %5;\n"
               "@p cp.async.bulk.tensor.2d.shared::cluster.global.mbarrier::complete_tx::bytes [%0], [%1, {%3, %4}], [%2];\n}"
               ::"r"(dst), "l"(tm), "r"(bar), "r"(c0), "r"(c1), "r"(expect) : "memory");
}
__device__ __forceinline__ void load_lin(uint32_t dst, const void* src, uint32_t bytes, uint32_t bar, uint32_t expect) {
  if (expect) asm volatile("{\n.reg .pred p;\nelect.sync _|p, 0xffffffff;\n@p mbarrier.arrive.expect_tx.shared::cta.b64 _, [%0], %1;\n}" ::"r"(bar), "r"(expect) : "memory");
  asm volatile("{\n.reg .pred p;\nelect.sync _|p, 0xffffffff;\n"
               "@p cp.async.bulk.shared::cluster.global.mbarrier::complete_tx::bytes [%0], [%1], %2, [%3];\n}" ::"r"(dst), "l"(src), "r"(bytes), "r"(bar) : "memory");
}
__host__ __device__ constexpr int p2slot(int j) { return (int)(((j < 16 ? 0x0675432CBA065432ull >> (4 * j) : 0xA1ull >> (4 * (j - 16)))) & 15); }
__host__ __device__ constexpr int ph(int s) { return s < 8 ? (0x32105476 >> (4 * s)) & 7 : s; }
__host__ __device__ constexpr int b0(int s) { return s < 6 ? 2 + (s & 3) : (s < 8 ? s : s - 4); }
__host__ __device__ constexpr int p2par(int j) { return (0x181DF >> j) & 1; }

__global__ void __cluster_dims__(2, 1, 1) __launch_bounds__(384, 1) fused_kernel(const __grid_constant__ Params P) {
  extern __shared__ __align__(1024) unsigned char smem_raw[];
  const uint32_t misc = s2u(smem_raw);
  if ((misc & 0x3FFFFu) != SM0) return;
  const uint32_t base = misc + 2048u;
  const uint32_t xb = base + XS * SLOT;
  const uint32_t rank = blockIdx.x & 1;
  const int pr = blockIdx.x >> 1;
  const int c = pr & 7;
  const int rb = (pr >> 3) * 2 + rank;
  const int lane = threadIdx.x & 31;
  const int warp = __shfl_sync(0xffffffffu, threadIdx.x >> 5, 0);
  const int wgid = warp >> 2;

  asm volatile("{\n.reg .pred p;\nelect.sync _|p, 0xffffffff;\n@p mbarrier.init.shared::cta.b64 [%0], 1;\n@p mbarrier.init.shared::cta.b64 [%0 + 112], 4;\n"
               "@p mbarrier.init.shared::cta.b64 [%1], %2;\n@p fence.mbarrier_init.release.cluster;\n}"
               ::"r"(misc + warp * 8), "r"(misc + (warp < 2 ? 12 + warp : 24 + warp) * 8), "r"((uint32_t)(0x382438384411ull >> (4 * warp)) & 15u) : "memory");
  if ((warp & 14) == 8) load_x(base + warp * SLOT, &P.x, misc + warp * 8, (warp & 1) * 64, rb * 128);
  if (warp == 10) prefetch_tm(&P.qkv);
  asm volatile("barrier.cluster.arrive.relaxed.aligned;" ::: "memory");
#define CLUSTER_WAIT() asm volatile("barrier.cluster.wait.aligned;" ::: "memory")

  if (wgid == 2) {
    asm volatile("setmaxnreg.dec.sync.aligned.u32 56;");
    if (warp == 8) {
      CLUSTER_WAIT();
      const int hh = 224 * c + ((c & 1) ? 0 : 192);
      const int hf = 224 * c + ((c & 1) ? 32 : 0);
      const uint32_t dst = base + rank * 8192;
      const uint4* axp = P.ax + (blockIdx.x ^ 2) * 4608;
#pragma unroll
      for (int s = 0; s < 8; s++) {
        const uint32_t bar = misc + OFF_FULL + b0(s) * 8;
        if (s >= 4) mbar_wait(misc + OFF_EMPTY + b0(s - 4) * 8, 0);
        load_mc(dst + (s & 3) * 24576, &P.qkv, bar, 512 + 512 * rank + 64 * c, s * 64, s ? 24576 : 24576 + 1024 + 16);
        if ((s & 1) == rank) load_mc2(base + (s & 3) * 24576 + 16384, &P.qkv, bar, 64 * c, s * 64);
        if (s == 0) {
          load_lin(misc + OFF_GW, P.gatew, 1024, bar, 0);
          load_lin(misc + OFF_EPOCH, P.epoch + blockIdx.x, 16, bar, 0);
        }
        if (s >= 2) {
          const int kb = s, xs = (kb < 6) ? XS + kb : kb - 6;
          load_x(base + ph(xs) * SLOT, &P.x, misc + OFF_FULL + xs * 8, kb * 64, rb * 128);
        }
        if (s == 3 && lane < 7) prefetch_tm(&P.g + lane);
      }
      TS(2, 0);
#pragma unroll
      for (int s = 0; s < 4; s++) {
        const int slot = s + 4;
        mbar_wait(misc + OFF_EMPTY + b0(slot) * 8, s < 2);
        load_mc(dst + ph(slot) * SLOT, &P.g32, misc + OFF_FULL + slot * 8, hh, s * 128 + rank * 64);
        load_mc2(dst + ph(slot) * SLOT + 4096, &P.u32, misc + OFF_FULL + slot * 8, hh, s * 128 + rank * 64);
      }
      {
        const CUtensorMap* tm = rank ? &P.u : &P.g;
#pragma unroll 1
        for (int t = 0; t < 3; t++) {
#pragma unroll
          for (int kb = 0; kb < 8; kb++) {
            const int slot = (kb + 2) & 7;
            mbar_wait(misc + OFF_EMPTY + slot * 8, (t + (kb < 6)) & 1);
            if (kb == 0 && t == 2) {
              asm volatile("{\n.reg .pred p;\nelect.sync _|p, 0xffffffff;\n@p mbarrier.expect_tx.relaxed.cta.shared::cta.b64 [%0], 8192;\n}" ::"r"(misc + OFF_FULL + slot * 8) : "memory");
              load_lin(xb + 4 * SLOT + 8192, axp, 8192, misc + OFF_FULL + slot * 8, 0);
            }
            load_mc(dst + ph(slot) * SLOT, tm, misc + OFF_FULL + slot * 8, hf + 64 * t, ((kb + 6) & 7) * 64);
          }
        }
      }
      TC(2, 2);
      const int hp = 224 * (c ^ 1) + ((c & 1) ? 0 : 32);
#pragma unroll
      for (int j = 0; j < 18; j++) {
        if (j == 5 || j == 8) {
          const int sl = j == 5 ? 7 : 1;
          mbar_wait(misc + OFF_EMPTY + sl * 8, j != 5);
          load_lin(base + ph(sl) * SLOT, axp + (j == 5 ? 512 : 1536), SLOT, misc + OFF_FULL + sl * 8, SLOT);
        }
        const int sl = p2slot(j), kbi = j % 9;
        mbar_wait(misc + OFF_EMPTY + sl * 8, p2par(j) ^ 1);
        const int col = ((c + 2 + (j >= 9 ? 4 : 0) + 2 * rank) & 7) * 64;
        if (kbi == 3 || kbi == 7) load_mc(dst + ph(sl) * SLOT, &P.wo, misc + OFF_FULL + sl * 8, col, 64 * (kbi == 3 ? c : c ^ 1));
        else load_mc(dst + ph(sl) * SLOT, &P.wd, misc + OFF_FULL + sl * 8, col, kbi < 3 ? hf + 64 * (kbi < 2 ? kbi ^ 1 : 2) : (kbi == 4 ? 448 * (c >> 1) + 192 : hp + 64 * (kbi == 8 ? 2 : kbi - 5)));
        TC(2, 8 + j);
      }
      TC(2, 3);
    } else {
      const int aw = warp - 9;
      CLUSTER_WAIT();
      mbar_wait(misc + OFF_FULL + 2 * 8, 0);
      const unsigned epoch = lds_u(misc + OFF_EPOCH);
      if (aw == 0) {
        float4* z = P.kv + ((epoch + 1) & 1) * (32 * 136) + blockIdx.x * 34;
        z[lane] = make_float4(0.f, 0.f, 0.f, 0.f);
        if (lane < 2) z[32 + lane] = make_float4(0.f, 0.f, 0.f, 0.f);
        if (lane == 0) P.epoch[blockIdx.x].x = epoch + 1;
      }
      uint32_t ra = xb + lane * 64 + (((lane >> 1) & 3) << 4);
      asm volatile("" : "+r"(ra));
      mbar_wait(misc + OFF_FULL + 1 * 8, 0);
      {
        uint4* o = reinterpret_cast<uint4*>(P.out + (size_t)(rb * 128 + (lane >> 3)) * 512 + c * 64) + (lane & 7);
#pragma unroll 1
        for (int i = aw; i < 32; i += 3) o[i * 256] = make_uint4(0u, 0u, 0u, 0u);
        asm volatile("fence.proxy.async;" ::: "memory");
      }
#pragma unroll 1
      for (int seg = 0; seg < 3; seg++) {
        mbar_wait(misc + (seg ? OFF_T1R : OFF_PKR), 0);
        TC(1, seg + 8 * aw);
        const int u1 = seg < 2 ? seg * 9 + aw * 3 + 3 : 20 + aw * 6;
        phi_rows(ra + (u1 - (seg < 2 ? 3 : (aw ? 6 : 2))) * 2048, ra + u1 * 2048);
        if (seg < 2) {
          fence_async();
          __syncwarp();
          if (lane == 0) mbar_arrive(misc + OFF_PHIK + seg * 48);
        }
      }
      if (aw == 0) {
        mbar_wait(misc + OFF_KVR + 16, 0);
        TC(1, 3);
        if (lane == 0) {
          asm volatile("fence.acq_rel.gpu;" ::: "memory");
          asm volatile("red.relaxed.gpu.global.add.u32 [%0], 1;" ::"l"(P.cnt + c * 32) : "memory");
          asm volatile("red.relaxed.gpu.global.add.u32 [%0], 4;" ::"l"(P.cnt + (8 + 2 * rb + (c & 1)) * 32) : "memory");
        }
        __syncwarp();
      }
      TC(1, 4 + 8 * aw);
      if (lane < 2) {
        const unsigned target = (epoch + 1) * 16u;
#pragma unroll 1
        for (int it = 0; it < (1 << 16); it++) {
          unsigned v;
          asm volatile("ld.acquire.gpu.global.u32 %0, [%1];" : "=r"(v) : "l"(P.cnt + (lane ? 8 + 2 * rb + (c & 1) : c) * 32) : "memory");
          if ((int)(v - target) >= 0) break;
          __nanosleep(32);
        }
      }
      __syncwarp();
      TC(1, 5 + 8 * aw);
      {
        const float4* kvg = P.kv + (epoch & 1) * (32 * 136) + 4 * c * 136;
        if (aw < 2) {
          float4 v[8];
#pragma unroll
          for (int j = 0; j < 8; j++) v[j] = __ldcg(kvg + (2 * aw + (j >> 2)) * 136 + (j & 3) * 32 + lane);
#pragma unroll
          for (int j = 0; j < 8; j++) {
            const uint32_t d = xb + 4 * SLOT + (2 * aw + (j >> 2)) * 1536 + (j & 2) * 128 + (j & 1) * 512 + lane * 4;
            sts32(d, pack2(v[j].x, v[j].y));
            sts32(d + 128, pack2(v[j].z, v[j].w));
          }
        } else {
          float zv[4];
#pragma unroll
          for (int j = 0; j < 4; j++) zv[j] = __ldcg(reinterpret_cast<const float*>(kvg + j * 136 + 128) + lane);
#pragma unroll
          for (int j = 0; j < 4; j++) {
            const uint32_t zz = pack2(zv[j], zv[j]);
            sts128(xb + 4 * SLOT + j * 1536 + 1024 + lane * 16, zz, zz, zz, zz);
          }
        }
      }
      fence_async();
      __syncwarp();
      if (lane == 0) mbar_arrive(misc + OFF_ORDY);
      TC(1, 6 + 8 * aw);
    }
  } else {
    asm volatile("setmaxnreg.inc.sync.aligned.u32 224;");
    const int tw = threadIdx.x & 127;
    const uint32_t park = xb + warp * 2048 + lane * 16;
    constexpr uint32_t dbase = (SM0 + 2048u) >> 4;
    const uint32_t dxh = dbase + ((XS * SLOT + wgid * 8192) >> 4);
#define prow (xb + wgid * 8192 + (warp & 3) * 1024 + (lane & 15) * 64 + (((lane >> 4) ^ ((lane >> 1) & 3)) << 4))
    uint4* const axo = P.ax + blockIdx.x * 4608 + warp * 128;
    const uint32_t wpark = xb + warp * 2048;
    uint32_t rel;
    asm volatile("mapa.shared::cluster.u32 %0, %1, %2;" : "=r"(rel) : "r"(misc + OFF_EMPTY), "r"(tw & 1));
    const bool sig = tw < 2;
#define RELEASE(slot) do { if (sig) asm volatile("mbarrier.arrive.shared::cluster.b64 _, [%0];" ::"r"(rel + (slot) * 8) : "memory"); } while (0)
    float omg0, omg1;
#define cmo ((lane & 8) * 128 + (lane & 16) * 8 + (lane & 7) * 16)
    uint32_t accA[32], accB[32];
    uint32_t xf[32][4];
    {
      {
        const uint32_t xrow = xb + (warp * 16 + (lane & 15)) * 128;
        const uint32_t xsw = lane & 7, xhi = lane >> 4;
        const uint4 wp = __ldg(reinterpret_cast<const uint4*>(P.wphi) + c * 128 + tw);
        CLUSTER_WAIT();
        mbar_wait(misc + OFF_FULL + XS * 8, 0);
#pragma unroll
        for (int k = 0; k < 4; k++) ldsm4(xf[k], xrow + (((2 * k + xhi) ^ xsw) << 4));
        TCC(0);
        if (wgid) {
#pragma unroll
          for (int i = 0; i < SKEW; i++) mbar_wait(misc + OFF_FULL + (2 + i) * 8, 0);
        }
        float gl[4];
        uint32_t w[96];
        constexpr uint32_t dgw = ((SM0 + OFF_GW) >> 4) | (1u << 16);
#pragma unroll
        for (int kb = 0; kb < 8; kb++) {
          const int kw = kb + SKEW;
          mbar_wait(misc + OFF_FULL + (wgid ? b0(kw) : b0(kb)) * 8, (0xF30 >> (wgid ? kw : kb)) & 1);
          const uint32_t d0 = (dbase + (kb & 3) * (24576 >> 4)) | ((8192u >> 4) << 16);
          WG_FENCE();
#pragma unroll
          for (int k = 0; k < 4; k++) {
            if (kb < 6) {
              wgmma192(w, xf[kb * 4 + k], d0 + k * 128, (kb | k) != 0);
              wgmma8(gl, xf[kb * 4 + k], dgw + (kb * 4 + k) * 2, (kb | k) != 0);
            } else {
              wgmma192_ss(w, dxh - ((XS - kb) * SLOT >> 4) + k * 2, d0 + k * 128);
              wgmma8_xs(gl, dxh - ((XS - kb) * SLOT >> 4) + k * 2, dgw + (kb * 4 + k) * 2);
            }
          }
          WG_COMMIT();
          if (kb > 0) {
            WG_WAIT(1);
            RELEASE(b0(kb - 1));
          }
          if (kb < 7) mbar_wait(misc + OFF_FULL + (kb < 5 ? XS + kb + 1 : kb - 5) * 8, 0);
          if (kb < 5) {
#pragma unroll
            for (int k = 0; k < 4; k++) ldsm4(xf[(kb + 1) * 4 + k], xrow + (kb + 1) * SLOT + (((2 * k + xhi) ^ xsw) << 4));
          }
          if (kb == 4) {
            __syncwarp();
            sts128(xb + 5 * SLOT + warp * 2048 + 1024 + (lane & 1) * 256 + (lane >> 1) * 16, wp.x, wp.y, wp.z, wp.w);
            if (tw < 8) sts128(misc + OFF_ONES + tw * 16, 0x3f803f80u, 0x3f803f80u, 0x3f803f80u, 0x3f803f80u);
          }
          if (kb == 5) {
            fence_async();
            asm volatile("bar.sync %0, 128;" ::"r"(1 + wgid) : "memory");
          }
        }
        WG_WAIT(0);
        fence_acc(w); fence_acc(gl);
        RELEASE(7);
        float pj[32], pq[32];
#pragma unroll
        for (int h = 0; h < 4; h++) pack_inplace(w + 8 * h);
#pragma unroll
        for (int h = 0; h < 4; h++) pack_inplace(w + 32 + 8 * h);
#pragma unroll
        for (int h = 0; h < 4; h++) pack_inplace(w + 64 + 8 * h);
#pragma unroll
        for (int h = 0; h < 4; h++) stsm4(park + 4 * SLOT + h * 512, w[32 + 8 * h], w[33 + 8 * h], w[34 + 8 * h], w[35 + 8 * h]);
#pragma unroll
        for (int i = 0; i < 32; i++) pj[i] = 0.f;
        WG_FENCE();
#pragma unroll
        for (int h = 0; h < 4; h++) wgmma16(pj + 8 * h, w + 8 * h, (dxh + ((5 * SLOT + h * 2048 + 1024) >> 4)) | DLBO128B);
        WG_COMMIT();
        fence_async();
        {
          const float l0 = __shfl_sync(0xffffffffu, gl[0], lane & 28), l1 = __shfl_sync(0xffffffffu, gl[2], lane & 28);
          omg0 = 1.0f - __fdividef(1.0f, 1.0f + __expf(-l0));
          omg1 = 1.0f - __fdividef(1.0f, 1.0f + __expf(-l1));
        }
        WG_WAIT(0);
        fence_acc(pj);
#pragma unroll
        for (int i = 0; i < 32; i++) pq[i] = 0.f;
        WG_FENCE();
#pragma unroll
        for (int h = 0; h < 4; h++) wgmma16(pq + 8 * h, w + 64 + 8 * h, (dxh + ((5 * SLOT + h * 2048 + 1024) >> 4)) | DLBO128B);
        WG_COMMIT();
        store_p(prow, pj);
        __syncwarp();
        if (lane == 0) mbar_arrive(misc + OFF_PKR);
        TCC(1);
        if (wgid) asm volatile("bar.sync 3, 256;" ::: "memory");
#pragma unroll
        for (int s = 0; s < 4; s++) {
          const int slot = s + 4;
          mbar_wait(misc + OFF_FULL + slot * 8, 1);
          WG_FENCE();
#pragma unroll
          for (int k = 0; k < 8; k++)
            wgmma64(accB, xf[s * 8 + k], (dbase + ph(slot) * (SLOT >> 4) + (k >> 2) * 512 + (k & 3) * 64) | DLBO64, DHI64, (s | k) != 0);
          WG_COMMIT();
          if (s == LAG - 1 && !wgid) asm volatile("bar.arrive 3, 256;" ::: "memory");
          WG_WAIT(1);
          if (s == 0) {
            fence_acc(pq);
            store_p(prow + 2 * SLOT, pq);
            __syncwarp();
            if (lane == 0) mbar_arrive(misc + OFF_T1R);
#pragma unroll
        for (int k = 0; k < 8; k++) ldsm4(xf[24 + k], xrow + ((k >> 2) - 2) * SLOT + (((2 * (k & 3) + xhi) ^ xsw) << 4));
          } else {
            RELEASE(slot - 1);
          }
        }
        const uint32_t tag = ~lds_u(misc + OFF_EPOCH) & 1u;
        WG_WAIT(0);
        fence_acc(accB);
        if (tw < 6) asm volatile("mbarrier.arrive.shared::cluster.b64 _, [%0];" ::"r"(rel + ((7 + (tw >> 1)) & 7) * 8) : "memory");
#pragma unroll
        for (int h = 0; h < 2; h++) {
          float v[8];
#pragma unroll
          for (int i = 0; i < 8; i++) v[i] = F(accB[8 * h + i]) * F(accB[16 + 8 * h + i]) * ((i & 2) ? omg1 : omg0);
          uint32_t r[4] = {pack2(v[0], v[1]), pack2(v[2], v[3]), pack2(v[4], v[5]), pack2(v[6], v[7])};
          set_tag(r[0], tag);
          sts128(park + 5 * SLOT + h * 512, r[0], r[1], r[2], r[3]);
        }
        redef(accA);
        TCC(2);
      }
#pragma unroll 1
      for (int t = 2;; t++) {
#pragma unroll
        for (int kb = 0; kb < 8; kb++) {
          if (kb == 7 && t == 4) break;
          mbar_wait(misc + OFF_FULL + ((kb + 2) & 7) * 8, (t + (kb >= 6)) & 1);
          const uint32_t d0 = dbase + ph((kb + 2) & 7) * (SLOT >> 4);
          WG_FENCE();
#pragma unroll
          for (int k = 0; k < 4; k++) {
            wgmma64(accA, xf[((kb + 6) & 7) * 4 + k], d0 + k * 128, DHI128, (kb | k) != 0);
            wgmma64(accB, xf[((kb + 6) & 7) * 4 + k], d0 + 512 + k * 128, DHI128, (kb | k) != 0);
          }
          WG_COMMIT();
          if (kb == 3 && t == 2) TCC(11);
          if (kb == 2) send_lin(axo + (t == 2 ? -warp * 64 : 1024 * t - 2560), wpark + (t == 2 ? 5 : t - 3) * SLOT, t == 2 ? 1024 : 2048);
          if (kb > 0) {
            WG_WAIT(1);
            RELEASE((kb + 1) & 7);
          }
        }
        if (t == 4) break;
        const uint32_t tag = ~lds_u(misc + OFF_EPOCH) & 1u;
        mbar_wait(misc + (t == 2 ? OFF_PHIK + wgid * 48 : OFF_KVR + 16), 0);
        mbar_wait(misc + (wgid ? OFF_KVR : OFF_PHIK), 0);
        if (t == 2) TCC(14);
        WG_WAIT(0);
        if (t == 2) TCC(15);
        fence_acc(accA); fence_acc(accB);
        RELEASE(1);
        {
#pragma unroll
          for (int i = 0; i < 32; i++) accA[i] = __float_as_uint(F(accA[i]) * F(accB[i]));
          fence_acc(accA);
          if (t == 2) {
            float kv[16], zz[4];
#pragma unroll
            for (int i = 0; i < 16; i++) kv[i] = 0.f;
#pragma unroll
            for (int i = 0; i < 4; i++) zz[i] = 0.f;
            fence_acc(zz);
            WG_FENCE();
#pragma unroll
            for (int k = 0; k < 8; k++) {
              const uint32_t da = (dbase + ((XS * SLOT + wgid * SLOT + (k >> 2) * 8192 + (k & 3) * 1024) >> 4)) | DLBO64;
              wgmma32_ss(kv, da, (dbase + (((XS + 4) * SLOT + k * 2048 + wgid * 1024) >> 4)) | DLBO128B, k != 0);
              wgmma8_ss(zz, da, (SM0 + OFF_ONES) >> 4);
            }
            WG_COMMIT();
#pragma unroll
            for (int i = 0; i < 32; i++) accA[i] = __float_as_uint(F(accA[i]) * ((i & 2) ? omg1 : omg0));
#pragma unroll
            for (int h = 0; h < 4; h++) { pack_inplace(accA + 8 * h); set_tag(accA[8 * h], tag); }
            WG_WAIT(0);
            fence_acc(kv); fence_acc(zz);
            if ((threadIdx.x & 159) == 0) mbar_arrive(misc + OFF_KVR);
            const bool hi = (warp & 2) != 0;
            float4* kvg = P.kv + ((tag ^ 1) * 32 + 4 * c + (warp >> 1)) * 136;
#pragma unroll
            for (int nt = 0; nt < 2; nt++) {
              const float* s = kv + 4 * nt;
              red4(kvg + (warp & 1) * 64 + lane + nt * 32, hi ? s[8] : s[0], hi ? s[9] : s[1], hi ? s[10] : s[2], hi ? s[11] : s[3]);
            }
            if (!(lane & 2))
              asm volatile("red.relaxed.gpu.global.add.f32 [%0], %1;"
                           ::"l"(reinterpret_cast<float*>(kvg + 128) + (warp & 1) * 16 + (lane & 1) * 8 + (lane >> 2)), "f"((lane & 1) ? zz[2] : zz[0]) : "memory");
            redef(accB);
            __syncwarp();
            if (lane == 0) mbar_arrive(misc + OFF_KVR + 16);
            mbar_wait(misc + OFF_KVR, 0);
#pragma unroll
            for (int h = 0; h < 4; h++) sts128(park + h * 512, accA[8 * h], accA[8 * h + 1], accA[8 * h + 2], accA[8 * h + 3]);
          } else {
#pragma unroll
            for (int i = 0; i < 32; i++) accA[i] = __float_as_uint(F(accA[i]) * ((i & 2) ? omg1 : omg0));
#pragma unroll
            for (int h = 0; h < 4; h++) pack_inplace(accA + 8 * h);
            const uint32_t keep = (lane & 3) ? 0xffffffffu : 0xfffffffeu, tg = tag & ~keep;
#pragma unroll
            for (int h = 0; h < 4; h++)
              stsm4(wpark + SLOT + cmo + h * 256, (accA[8 * h] & keep) | tg, (accA[8 * h + 1] & keep) | tg, (accA[8 * h + 2] & keep) | tg, (accA[8 * h + 3] & keep) | tg);
          }
        }
        TCC(1 + t);
      }
    }

    uint32_t af[36][4];
    const uint4* const axp = P.ax + (blockIdx.x ^ 2) * 4608 + warp * 128 + lane;
    const uint32_t mo = (c & 1) * 256u, mp = 256u - mo;
    const uint32_t tag = ~lds_u(misc + OFF_EPOCH) & 1u;
    const uint32_t da1 = (dxh + (SLOT >> 4)) | DLBO128B;
#define P2WAIT(j) mbar_wait(misc + OFF_FULL + p2slot(j) * 8, p2par(j))
#define P2DESC(j, kb, k) (dbase + ph(p2slot(j)) * (SLOT >> 4) + ((kb) == 4 ? ((k) < 2 ? mo : mp) + ((k) & 1) * 128 : (k) * 128))
    {
      float nm[4][12];
#pragma unroll
      for (int i = 0; i < 2; i++) lds128(af[16 + i], park + 5 * SLOT + i * 512);
#pragma unroll
      for (int i = 0; i < 2; i++) lds128(af[18 + i], park - warp * 1024 + 4 * SLOT + 8192 + i * 512);
      mbar_wait(misc + OFF_ORDY, 0);
      mbar_wait(misc + OFF_FULL + 1 * 8, 1);
      WG_FENCE();
#pragma unroll
      for (int h = 0; h < 4; h++) {
#pragma unroll
        for (int ks = 0; ks < 2; ks++)
          wgmma24_ss(nm[h], dxh + (((2 + (h >> 1)) * SLOT + (h & 1) * 4096 + ks * 32) >> 4), (dbase + (((XS + 4) * SLOT + h * 1536 + ks * 256) >> 4)) | DLBO128B, ks);
      }
      WG_COMMIT();
      recv_check<2>(af + 18, axp - warp * 64, tag);
      WG_FENCE();
#pragma unroll
      for (int k = 0; k < 4; k++) {
        wgmma64(accA, xf[20 + k], dbase + ph(1) * (SLOT >> 4) + k * 128, DHI128, 1);
        wgmma64(accB, xf[20 + k], dbase + ph(1) * (SLOT >> 4) + 512 + k * 128, DHI128, 1);
      }
      WG_COMMIT();
      send_wait<0>();
      WG_WAIT(1);
      if (tw < 6) asm volatile("mbarrier.arrive.shared::cluster.b64 _, [%0];" ::"r"(rel + ((0xBA0u >> (4 * (tw >> 1))) & 15) * 8) : "memory");
#pragma unroll
      for (int h = 0; h < 4; h++) {
        fence_acc(nm[h]);
        const float f0 = (1.0f - omg0) * rcp(nm[h][8] + 1e-6f), f1 = (1.0f - omg1) * rcp(nm[h][10] + 1e-6f);
        af[12 + h][0] = pack2(nm[h][0] * f0, nm[h][1] * f0); af[12 + h][1] = pack2(nm[h][2] * f1, nm[h][3] * f1);
        af[12 + h][2] = pack2(nm[h][4] * f0, nm[h][5] * f0); af[12 + h][3] = pack2(nm[h][6] * f1, nm[h][7] * f1);
        set_tag(af[12 + h][0], tag);
        sts128(park + 5 * SLOT + h * 512, af[12 + h][0], af[12 + h][1], af[12 + h][2], af[12 + h][3]);
      }
#pragma unroll
      for (int i = 0; i < 4; i++) lds128(af[4 + i], park + i * 512);
      P2WAIT(0);
      WG_WAIT(0);
      fence_acc(accA); fence_acc(accB);
      if (tw < 4) asm volatile("mbarrier.arrive.shared::cluster.b64 _, [%0];" ::"r"(rel + ((tw & 2) ? 12 : 1) * 8) : "memory");
      TCC(5);
#pragma unroll
      for (int i = 0; i < 32; i++) accA[i] = __float_as_uint(F(accA[i]) * F(accB[i]));
      fence_acc(accA);
      WG_FENCE();
#pragma unroll
      for (int k = 0; k < 4; k++) wgmma64_ss(accB, da1 + k * 16, P2DESC(0, 0, k) + 512, k != 0);
      send_lin(axo + 2560, wpark + 5 * SLOT, 2048);
#pragma unroll
      for (int h = 0; h < 4; h++) {
        float v[8];
#pragma unroll
        for (int i = 0; i < 8; i++) v[i] = F(accA[8 * h + i]) * ((i & 2) ? omg1 : omg0);
#pragma unroll
        for (int e = 0; e < 4; e++) af[8 + h][e] = pack2(v[2 * e], v[2 * e + 1]);
        set_tag(af[8 + h][0], tag);
        sts128(park + h * 512, af[8 + h][0], af[8 + h][1], af[8 + h][2], af[8 + h][3]);
      }
      WG_FENCE();
#pragma unroll
      for (int k = 0; k < 4; k++) wgmma64_ss(accA, da1 + k * 16, P2DESC(0, 0, k), k != 0);
      WG_COMMIT();
    }
    TCC(6);
#pragma unroll
    for (int kb = 1; kb < 9; kb++) {
      P2WAIT(kb);
      if (kb == 4) recv_check<4>(af + 20, axp + 512, tag);
      if (kb == 6) {
        int it = 0;
#pragma unroll 1
        while (true) {
          uint32_t bad = 0;
#pragma unroll
          for (int i = 0; i < 16; i++) bad |= af[24 + (i >> 2)][i & 3] ^ tag;
          if (!__any_sync(0xffffffffu, (bad & 1) && !(lane & 3)) || ++it > (1 << 16)) break;
          const uint32_t* g = reinterpret_cast<const uint32_t*>(axp - lane + 1536) + lane;
#pragma unroll
          for (int i = 0; i < 16; i++)
            asm volatile("ld.relaxed.gpu.global.u32 %0, [%1];" : "=r"(af[24 + (i >> 2)][i & 3]) : "l"(g + (i & 1) * 256 + (i & 2) * 16 + (i >> 2) * 64) : "memory");
        }
      }
      if (kb >= 7) { recv_check<4>(af + 4 * kb, axp + 2560 + (kb - 7) * 1024, tag); TCC(kb == 7 ? 7 : 10); }
      WG_FENCE();
#pragma unroll
      for (int k = 0; k < 4; k++) {
        wgmma64(accA, af[4 * kb + k], P2DESC(kb, kb, k), DHI128, 1);
        wgmma64(accB, af[4 * kb + k], P2DESC(kb, kb, k) + 512, DHI128, 1);
      }
      WG_COMMIT();
      if (kb == 1) send_lin(axo + 3584, wpark, 2048);
      if (kb == 3) {
        mbar_wait(misc + OFF_FULL + 7 * 8, 1);
#pragma unroll
        for (int i = 0; i < 4; i++) lds128(af[20 + i], park - (XS - ph(7)) * SLOT + i * 512);
      }
      if (kb == 5) {
        mbar_wait(misc + OFF_FULL + 1 * 8, 0);
#pragma unroll
        for (int i = 0; i < 4; i++) ldsm4(af[24 + i], wpark - (XS - ph(1)) * SLOT + cmo + i * 256);
      }
      if (kb == 5) recv_issue<4>(af + 28, axp + 2560);
      if (kb == 7) recv_issue<4>(af + 32, axp + 3584);
      if (kb < 8) {
        WG_WAIT(1);
        RELEASE(p2slot(kb - 1));
        if (kb == 5) RELEASE(7);
        if (kb == 7) RELEASE(1);
      }
    }
    const uint32_t orow = wpark + (lane & 15) * 128 + (((lane >> 4) ^ (lane & 7)) << 4);
    const int orow0 = rb * 128 + warp * 16;
    send_wait<0>();
    WG_WAIT(0);
    fence_acc(accA); fence_acc(accB);
    stage_piece(orow, accA);
    TCC(8);
#pragma unroll
    for (int kb = 0; kb < 9; kb++) {
      P2WAIT(9 + kb);
      WG_FENCE();
#pragma unroll
      for (int k = 0; k < 4; k++) {
        if (kb == 0) wgmma64_ss(accA, da1 + k * 16, P2DESC(9, 0, k), k != 0);
        else wgmma64(accA, af[4 * kb + k], P2DESC(9 + kb, kb, k), DHI128, 1);
      }
      if (kb == 1) send_add(&P.o, wpark, ((c + 2) & 7) * 64, orow0);
      if (kb == 3) { stage_piece(orow + 5 * SLOT, accB); send_add(&P.o, wpark + 5 * SLOT, ((c + 4) & 7) * 64, orow0); }
    }
    WG_COMMIT();
#pragma unroll
    for (int kb = 0; kb < 9; kb++) {
      WG_FENCE();
#pragma unroll
      for (int k = 0; k < 4; k++) {
        if (kb == 0) wgmma64_ss(accB, da1 + k * 16, P2DESC(9, 0, k) + 512, k != 0);
        else wgmma64(accB, af[4 * kb + k], P2DESC(9 + kb, kb, k) + 512, DHI128, 1);
      }
      if (kb == 1) {
        WG_COMMIT();
        send_wait<1>();
        WG_WAIT(1);
        fence_acc(accA);
        stage_piece(orow, accA);
        send_add(&P.o, wpark, ((c + 6) & 7) * 64, orow0);
        TCC(9);
      }
    }
    WG_COMMIT();
    send_wait<1>();
    WG_WAIT(0);
    fence_acc(accB);
    TCC(12);
    stage_piece(orow + 5 * SLOT, accB);
    send_add(&P.o, wpark + 5 * SLOT, c * 64, orow0);
    send_wait<0>();
    TCC(13);
    if (warp == 4) TS(2, 4);
  }
}

typedef CUresult (*EncFn)(CUtensorMap*, CUtensorMapDataType, cuuint32_t, void*, const cuuint64_t*, const cuuint64_t*, const cuuint32_t*,
                          const cuuint32_t*, CUtensorMapInterleave, CUtensorMapSwizzle, CUtensorMapL2promotion, CUtensorMapFloatOOBfill);

void make_map(EncFn enc, CUtensorMap* m, const void* p, int rows, int cols, int bcols, int brows, CUtensorMapSwizzle sw) {
  cuuint64_t gd[2] = {(cuuint64_t)cols, (cuuint64_t)rows};
  cuuint64_t gs[1] = {(cuuint64_t)cols * 2};
  cuuint32_t bd[2] = {(cuuint32_t)bcols, (cuuint32_t)brows};
  cuuint32_t es[2] = {1, 1};
  enc(m, CU_TENSOR_MAP_DATA_TYPE_BFLOAT16, 2, const_cast<void*>(p), gd, gs, bd, es, CU_TENSOR_MAP_INTERLEAVE_NONE, sw,
      CU_TENSOR_MAP_L2_PROMOTION_L2_256B, CU_TENSOR_MAP_FLOAT_OOB_FILL_NONE);
}

}

extern "C" void kernel_launch(void* const* d_in, const int* in_sizes, int n_in, void* d_out, int out_size) {
  (void)in_sizes; (void)n_in; (void)out_size;
  void* fn = nullptr;
  cudaDriverEntryPointQueryResult qr;
  cudaGetDriverEntryPoint("cuTensorMapEncodeTiled", &fn, cudaEnableDefault, &qr);
  EncFn enc = (EncFn)fn;
  Params P;
  make_map(enc, &P.x,    d_in[0], 2048, 512,  64, 128, CU_TENSOR_MAP_SWIZZLE_128B);
  make_map(enc, &P.qkv,  d_in[1], 512,  1536, 64, 64,  CU_TENSOR_MAP_SWIZZLE_128B);
  make_map(enc, &P.g,    d_in[5], 512,  1792, 64, 64,  CU_TENSOR_MAP_SWIZZLE_128B);
  make_map(enc, &P.u,    d_in[6], 512,  1792, 64, 64,  CU_TENSOR_MAP_SWIZZLE_128B);
  make_map(enc, &P.g32,  d_in[5], 512,  1792, 32, 64,  CU_TENSOR_MAP_SWIZZLE_64B);
  make_map(enc, &P.u32,  d_in[6], 512,  1792, 32, 64,  CU_TENSOR_MAP_SWIZZLE_64B);
  make_map(enc, &P.wo,   d_in[3], 512,  512,  64, 64,  CU_TENSOR_MAP_SWIZZLE_128B);
  make_map(enc, &P.wd,   d_in[7], 1792, 512,  64, 64,  CU_TENSOR_MAP_SWIZZLE_128B);
  make_map(enc, &P.o,    d_out,   2048, 512,  64, 16,  CU_TENSOR_MAP_SWIZZLE_128B);
  cudaGetSymbolAddress((void**)&P.kv, g_kv);
  cudaGetSymbolAddress((void**)&P.cnt, g_cnt);
  cudaGetSymbolAddress((void**)&P.epoch, g_epoch);
  cudaGetSymbolAddress((void**)&P.ax, g_ax);
  P.wphi = (const __nv_bfloat16*)d_in[2];
  P.gatew = (const __nv_bfloat16*)d_in[8];
  P.out = (__nv_bfloat16*)d_out;
  cudaFuncSetAttribute(fused_kernel, cudaFuncAttributeMaxDynamicSharedMemorySize, SMEM_BYTES);
  cudaLaunchConfig_t cfg = {};
  cfg.gridDim = dim3(128);
  cfg.blockDim = dim3(384);
  cfg.dynamicSmemBytes = SMEM_BYTES;
  cfg.stream = cudaStreamPerThread;
  cudaLaunchAttribute at[1];
  at[0].id = cudaLaunchAttributeClusterDimension;
  at[0].val.clusterDim.x = 2; at[0].val.clusterDim.y = 1; at[0].val.clusterDim.z = 1;
  cfg.attrs = at;
  cfg.numAttrs = 1;
  cudaLaunchKernelEx(&cfg, fused_kernel, P);
}
```
